```python
import torch

def _softmax(x, axis=-1):
    return torch.softmax(x, dim=axis)
def _gelu(x):
    return torch.nn.functional.gelu(x, approximate="tanh")
def _silu(x):
    return torch.nn.functional.silu(x)
def _sigmoid(x):
    return torch.sigmoid(x)
def _layernorm(x, axis=-1, eps=1e-5):
    m = x.mean(dim=axis, keepdim=True)
    v = x.var(dim=axis, keepdim=True, unbiased=False)
    return (x - m) / torch.sqrt(v + eps)
def _scatter_add(tgt, idx, src, axis=0):
    return tgt.clone().index_add_(axis, idx, src)
def _segment_sum(src, seg, n):
    out = torch.zeros((n,) + src.shape[1:], dtype=src.dtype)
    return out.index_add_(0, seg, src)
def _pad(x, pw):
    flat = tuple(v for pair in reversed(pw) for v in pair)
    return torch.nn.functional.pad(x, flat)

kernel_name = 'standalone__low_rank_proj_linformer__decode'

def setup_inputs():

    _w = (lambda a: (lambda t: t.to(torch.bfloat16) if t.is_floating_point() else t)(torch.as_tensor(a)))
    B, H, Sq, Skv, Dh, R = 1, 32, 1, 4096, 192, 64
    return {
        "q": _w((lambda *s: torch.randn(*s, dtype=torch.bfloat16) * 0.8)(B, H, Sq, Dh)),
        "k": _w((lambda *s: torch.randn(*s, dtype=torch.bfloat16) * 0.8)(B, H, Skv, Dh)),
        "v": _w((lambda *s: torch.randn(*s, dtype=torch.bfloat16) * 0.05)(B, H, Skv, Dh)),
        "e_proj": _w((lambda *s: torch.randn(*s, dtype=torch.bfloat16) * 0.8)(R, Skv) * (Skv ** -0.5)),
        "f_proj": _w((lambda *s: torch.randn(*s, dtype=torch.bfloat16) * 0.05)(R, Skv) * (Skv ** -0.5)),
    }

def reference(q, k, v, e_proj, f_proj):
    B, H, Sq, Dh = q.shape
    kp = torch.einsum("rn,bhnd->bhrd", e_proj, k)
    vp = torch.einsum("rn,bhnd->bhrd", f_proj, v)
    scores = torch.einsum("bhqd,bhrd->bhqr", q, kp) * (Dh ** -0.5)
    p = _softmax(scores, axis=-1)
    o = torch.einsum("bhqr,bhrd->bhqd", p, vp)
    return o
```

```cpp
#include <cuda_runtime.h>
#include <cuda_bf16.h>
#include <cuda.h>
#include <stdint.h>

namespace lf {

constexpr int H = 32, SEQ = 4096, D = 192, R = 64;
constexpr int BOX = 8192;
constexpr int STAGE = 4 * BOX;
constexpr int NS = 5;
constexpr int CS = 12;
constexpr int V0 = 48;
constexpr int TAIL_ROW = (V0 - CS) * 64;
constexpr int KT = SEQ / 64 / 4;
constexpr int VT = (SEQ / 64 - CS) / 4;
constexpr int RT = KT + VT;
constexpr int RING = NS * STAGE;
constexpr int Q_BYTES = H * D * 2;
constexpr int SMEM_BYTES = RING + 2432 + CS * 256 + Q_BYTES;
__host__ __device__ constexpr int slot(int i) { return (i + NS - RT % NS) % NS; }
constexpr int SPIN_LIMIT = 1 << 22;
static_assert(CS % 4 == 0 && CS / 4 <= NS, "tail boxes must fit in the ring");
static_assert(V0 >= CS && V0 <= 64, "tail rows must not wrap");

struct __align__(256) Scratch {
    unsigned score[H * (SEQ / 64) * R];
    unsigned opart[H * 4 * D];
    unsigned epoch[H * 4];
};
__device__ Scratch g_scratch;

struct Pace {
    int tile;
    int lead;
    int slack;
    int box;
};

__device__ __forceinline__ uint32_t lds32(uint32_t a) {
    uint32_t v;
    asm volatile("ld.volatile.shared.b32 %0, [%1];" : "=r"(v) : "r"(a) : "memory");
    return v;
}
__device__ __forceinline__ float2 lds64f(uint32_t a) {
    float2 v;
    asm volatile("ld.shared.v2.f32 {%0, %1}, [%2];" : "=f"(v.x), "=f"(v.y) : "r"(a) : "memory");
    return v;
}
__device__ __forceinline__ uint4 lds128(uint32_t a) {
    uint4 v;
    asm volatile("ld.shared.v4.b32 {%0, %1, %2, %3}, [%4];" : "=r"(v.x), "=r"(v.y), "=r"(v.z), "=r"(v.w) : "r"(a) : "memory");
    return v;
}
__device__ __forceinline__ void sts32(uint32_t a, uint32_t v) { asm volatile("st.shared.b32 [%0], %1;" ::"r"(a), "r"(v) : "memory"); }
__device__ __forceinline__ void sts64f(uint32_t a, float x, float y) {
    asm volatile("st.shared.v2.f32 [%0], {%1, %2};" ::"r"(a), "f"(x), "f"(y) : "memory");
}
__device__ __forceinline__ unsigned now_ns() {
    unsigned t;
    asm volatile("mov.u32 %0, %globaltimer_lo;" : "=r"(t));
    return t;
}
__device__ __forceinline__ bool elect_one() {
    uint32_t pred;
    asm volatile("{\n.reg .pred p;\nelect.sync _|p, 0xffffffff;\nselp.u32 %0, 1, 0, p;\n}" : "=r"(pred));
    return pred;
}
__device__ __forceinline__ void proxy_fence() { asm volatile("fence.proxy.async.shared::cta;" ::: "memory"); }
__device__ __forceinline__ void mbar_init(uint32_t bar, uint32_t cnt) {
    asm volatile("mbarrier.init.shared::cta.b64 [%0], %1;" ::"r"(bar), "r"(cnt) : "memory");
}
__device__ __forceinline__ void mbar_expect_tx(uint32_t bar, uint32_t bytes) {
    asm volatile("mbarrier.arrive.expect_tx.shared::cta.b64 _, [%0], %1;" ::"r"(bar), "r"(bytes) : "memory");
}
__device__ __forceinline__ void mbar_arrive(uint32_t bar) {
    asm volatile("mbarrier.arrive.shared::cta.b64 _, [%0];" ::"r"(bar) : "memory");
}
__device__ __forceinline__ bool mbar_test(uint32_t bar) {
    uint32_t ok;
    asm volatile("{\n.reg .pred p;\nmbarrier.test_wait.parity.shared::cta.b64 p, [%1], 0;\nselp.u32 %0, 1, 0, p;\n}"
                 : "=r"(ok) : "r"(bar) : "memory");
    return ok;
}
__device__ __forceinline__ bool mbar_try(uint32_t bar) {
    uint32_t ok;
    asm volatile("{\n.reg .pred p;\nmbarrier.try_wait.parity.shared::cta.b64 p, [%1], 0;\nselp.u32 %0, 1, 0, p;\n}"
                 : "=r"(ok) : "r"(bar) : "memory");
    return ok;
}
__device__ __forceinline__ void mbar_wait(uint32_t bar) {
    int spins = 0;
    while (!mbar_try(bar)) {
        if (++spins > SPIN_LIMIT) __trap();
    }
}
__device__ __forceinline__ uint64_t stream_policy() {
    uint64_t pol;
    asm volatile("createpolicy.fractional.L2::evict_first.b64 %0, 1.0;" : "=l"(pol));
    return pol;
}
__device__ __forceinline__ void tma2d(uint32_t dst, const CUtensorMap* m, int c0, int c1, uint32_t bar) {
    asm volatile("cp.async.bulk.tensor.2d.shared::cluster.global.mbarrier::complete_tx::bytes [%0], [%1, {%3, %4}], [%2];"
                 ::"r"(dst), "l"(m), "r"(bar), "r"(c0), "r"(c1) : "memory");
}
__device__ __forceinline__ void tma2d_stream(uint32_t dst, const CUtensorMap* m, int c0, int c1, uint32_t bar, uint64_t pol) {
    asm volatile("cp.async.bulk.tensor.2d.shared::cluster.global.mbarrier::complete_tx::bytes.L2::cache_hint [%0], [%1, {%3, %4}], [%2], %5;"
                 ::"r"(dst), "l"(m), "r"(bar), "r"(c0), "r"(c1), "l"(pol) : "memory");
}
__device__ __forceinline__ void l2_prefetch(const void* p, uint32_t bytes) {
    asm volatile("cp.async.bulk.prefetch.L2.global [%0], %1;" ::"l"(p), "r"(bytes) : "memory");
}
__device__ __forceinline__ void map_prefetch(const CUtensorMap* m) { asm volatile("prefetch.tensormap [%0];" ::"l"(m) : "memory"); }
__device__ __forceinline__ void publish(unsigned* p, float v, unsigned par) {
    asm volatile("st.relaxed.gpu.global.b32 [%0], %1;" ::"l"(p), "r"((__float_as_uint(v) & ~1u) | par) : "memory");
}
template <int N>
__device__ __forceinline__ float2 gather(const unsigned* src, int stride, unsigned par) {
    unsigned w[2 * N], diff;
    int spins = 0;
#pragma unroll 1
    do {
        if (++spins > SPIN_LIMIT) __trap();
#pragma unroll
        for (int c = 0; c < N; c++)
            asm volatile("ld.relaxed.gpu.global.v2.b32 {%0, %1}, [%2];" : "=r"(w[2 * c]), "=r"(w[2 * c + 1]) : "l"(src + c * stride) : "memory");
        unsigned any = 0, all = 1;
#pragma unroll
        for (int c = 0; c < 2 * N; c++) { any |= w[c]; all &= w[c]; }
        diff = ((par ? all : any) ^ par) & 1;
    } while (__any_sync(0xffffffffu, diff));
    float2 r = make_float2(0.f, 0.f);
#pragma unroll
    for (int c = 0; c < N; c++) { r.x += __uint_as_float(w[2 * c] & ~1u); r.y += __uint_as_float(w[2 * c + 1] & ~1u); }
    return r;
}
__device__ __forceinline__ float quad_sum(float v) {
    v += __shfl_xor_sync(0xffffffffu, v, 1);
    return v + __shfl_xor_sync(0xffffffffu, v, 2);
}
__device__ __forceinline__ float bf_lo(uint32_t v) { return __uint_as_float(v << 16); }
__device__ __forceinline__ float bf_hi(uint32_t v) { return __uint_as_float(v & 0xffff0000u); }
__device__ __forceinline__ uint64_t make_desc(uint32_t addr, uint32_t lbo, uint32_t sbo) {
    return (uint64_t)((addr & 0x3FFFF) >> 4) | ((uint64_t)(lbo >> 4) << 16) | ((uint64_t)(sbo >> 4) << 32) | (1ull << 62);
}
__device__ __forceinline__ void wg_fence() { asm volatile("wgmma.fence.sync.aligned;" ::: "memory"); }
__device__ __forceinline__ void wg_commit() { asm volatile("wgmma.commit_group.sync.aligned;" ::: "memory"); }
__device__ __forceinline__ void wg_wait0() { asm volatile("wgmma.wait_group.sync.aligned 0;" ::: "memory"); }
template <int N>
__device__ __forceinline__ void acc_fence(float* d) {
#pragma unroll
    for (int i = 0; i < N; i++) asm volatile("" : "+f"(d[i])::"memory");
}
__device__ __forceinline__ void ldsm4t(uint32_t* a, uint32_t addr) {
    asm volatile("ldmatrix.sync.aligned.m8n8.x4.trans.shared.b16 {%0, %1, %2, %3}, [%4];"
                 : "=r"(a[0]), "=r"(a[1]), "=r"(a[2]), "=r"(a[3]) : "r"(addr) : "memory");
}
__device__ __forceinline__ void mma16816(float* d, const uint32_t* a, uint32_t b0, uint32_t b1) {
    asm volatile("mma.sync.aligned.m16n8k16.row.col.f32.bf16.bf16.f32 {%0, %1, %2, %3}, {%4, %5, %6, %7}, {%8, %9}, {%0, %1, %2, %3};"
                 : "+f"(d[0]), "+f"(d[1]), "+f"(d[2]), "+f"(d[3])
                 : "r"(a[0]), "r"(a[1]), "r"(a[2]), "r"(a[3]), "r"(b0), "r"(b1));
}
__device__ __forceinline__ void wgmma_n192_bt(float* d, uint64_t da, uint64_t db, int accumulate) {
    asm volatile(
        "{\n.reg .pred p;\n"
        "setp.ne.b32 p, %98, 0;\n"
        "wgmma.mma_async.sync.aligned.m64n192k16.f32.bf16.bf16 "
        "{%0, %1, %2, %3, %4, %5, %6, %7, %8, %9, %10, %11, %12, %13, %14, %15, "
        "%16, %17, %18, %19, %20, %21, %22, %23, %24, %25, %26, %27, %28, %29, %30, %31, "
        "%32, %33, %34, %35, %36, %37, %38, %39, %40, %41, %42, %43, %44, %45, %46, %47, "
        "%48, %49, %50, %51, %52, %53, %54, %55, %56, %57, %58, %59, %60, %61, %62, %63, "
        "%64, %65, %66, %67, %68, %69, %70, %71, %72, %73, %74, %75, %76, %77, %78, %79, "
        "%80, %81, %82, %83, %84, %85, %86, %87, %88, %89, %90, %91, %92, %93, %94, %95}, "
        "%96, %97, p, 1, 1, 0, 1;\n}\n"
        : "+f"(d[0]), "+f"(d[1]), "+f"(d[2]), "+f"(d[3]), "+f"(d[4]), "+f"(d[5]), "+f"(d[6]), "+f"(d[7]),
          "+f"(d[8]), "+f"(d[9]), "+f"(d[10]), "+f"(d[11]), "+f"(d[12]), "+f"(d[13]), "+f"(d[14]), "+f"(d[15]),
          "+f"(d[16]), "+f"(d[17]), "+f"(d[18]), "+f"(d[19]), "+f"(d[20]), "+f"(d[21]), "+f"(d[22]), "+f"(d[23]),
          "+f"(d[24]), "+f"(d[25]), "+f"(d[26]), "+f"(d[27]), "+f"(d[28]), "+f"(d[29]), "+f"(d[30]), "+f"(d[31]),
          "+f"(d[32]), "+f"(d[33]), "+f"(d[34]), "+f"(d[35]), "+f"(d[36]), "+f"(d[37]), "+f"(d[38]), "+f"(d[39]),
          "+f"(d[40]), "+f"(d[41]), "+f"(d[42]), "+f"(d[43]), "+f"(d[44]), "+f"(d[45]), "+f"(d[46]), "+f"(d[47]),
          "+f"(d[48]), "+f"(d[49]), "+f"(d[50]), "+f"(d[51]), "+f"(d[52]), "+f"(d[53]), "+f"(d[54]), "+f"(d[55]),
          "+f"(d[56]), "+f"(d[57]), "+f"(d[58]), "+f"(d[59]), "+f"(d[60]), "+f"(d[61]), "+f"(d[62]), "+f"(d[63]),
          "+f"(d[64]), "+f"(d[65]), "+f"(d[66]), "+f"(d[67]), "+f"(d[68]), "+f"(d[69]), "+f"(d[70]), "+f"(d[71]),
          "+f"(d[72]), "+f"(d[73]), "+f"(d[74]), "+f"(d[75]), "+f"(d[76]), "+f"(d[77]), "+f"(d[78]), "+f"(d[79]),
          "+f"(d[80]), "+f"(d[81]), "+f"(d[82]), "+f"(d[83]), "+f"(d[84]), "+f"(d[85]), "+f"(d[86]), "+f"(d[87]),
          "+f"(d[88]), "+f"(d[89]), "+f"(d[90]), "+f"(d[91]), "+f"(d[92]), "+f"(d[93]), "+f"(d[94]), "+f"(d[95])
        : "l"(da), "l"(db), "r"(accumulate));
}
__device__ __forceinline__ void wgmma_n64_at(float* d, uint64_t da, uint64_t db, int accumulate) {
    asm volatile(
        "{\n.reg .pred p;\n"
        "setp.ne.b32 p, %34, 0;\n"
        "wgmma.mma_async.sync.aligned.m64n64k16.f32.bf16.bf16 "
        "{%0, %1, %2, %3, %4, %5, %6, %7, %8, %9, %10, %11, %12, %13, %14, %15, "
        "%16, %17, %18, %19, %20, %21, %22, %23, %24, %25, %26, %27, %28, %29, %30, %31}, "
        "%32, %33, p, 1, 1, 1, 0;\n}\n"
        : "+f"(d[0]), "+f"(d[1]), "+f"(d[2]), "+f"(d[3]), "+f"(d[4]), "+f"(d[5]), "+f"(d[6]), "+f"(d[7]),
          "+f"(d[8]), "+f"(d[9]), "+f"(d[10]), "+f"(d[11]), "+f"(d[12]), "+f"(d[13]), "+f"(d[14]), "+f"(d[15]),
          "+f"(d[16]), "+f"(d[17]), "+f"(d[18]), "+f"(d[19]), "+f"(d[20]), "+f"(d[21]), "+f"(d[22]), "+f"(d[23]),
          "+f"(d[24]), "+f"(d[25]), "+f"(d[26]), "+f"(d[27]), "+f"(d[28]), "+f"(d[29]), "+f"(d[30]), "+f"(d[31])
        : "l"(da), "l"(db), "r"(accumulate));
}

template <bool SWEEP>
__global__ void __launch_bounds__(320, 1)
linformer_kernel(const __nv_bfloat16* __restrict__ k, const __nv_bfloat16* __restrict__ q,
                 const __nv_bfloat16* __restrict__ f, __nv_bfloat16* __restrict__ out,
                 Scratch* __restrict__ sc, const Pace pace,
                 const __grid_constant__ CUtensorMap mk, const __grid_constant__ CUtensorMap me,
                 const __grid_constant__ CUtensorMap mv, const __grid_constant__ CUtensorMap mf) {
    extern __shared__ __align__(1024) uint8_t smem[];
    const int cta = blockIdx.x, h = cta >> 2, j = cta & 3;
    auto ktile = [&](int i) { return SWEEP ? i * 128 + cta : h * 64 + i * 4 + j; };
    asm volatile("prefetch.global.L2 [%0];" ::"l"(reinterpret_cast<const char*>(k) + (unsigned)ktile(0) * (unsigned)(64 * D * 2) + threadIdx.x * 64) : "memory");

    uint32_t s0;
    asm volatile("mov.u32 %0, %1;" : "=r"(s0) : "r"((uint32_t)__cvta_generic_to_shared(smem)));
    const uint32_t full = s0 + RING, empty = full + 8 * 32, cfull = empty + 8 * 32;
    const uint32_t pready = cfull + 8 * 16, sready = pready + 8, setup = sready + 8, par_s = setup + 8, t0_s = par_s + 4;
    const uint32_t iss_s = s0 + RING + 768, p_s = iss_s + 128, r_s = p_s + 4 * R, s_s = r_s + 4 * 64;
    const uint32_t w_s = s_s + 16 * R, q_s = w_s + CS * 256;

    auto issue = [&](int i, uint64_t pol) {
        const uint32_t dst = s0 + slot(i) * STAGE, bar = full + 8 * i;
        mbar_expect_tx(bar, STAGE);
        const bool isk = i < KT;
        const int row = (isk ? ktile(i) : h * 64 + ((i * 4 + j + V0) & 63)) * 64;
        const CUtensorMap* m = isk ? &mk : &mv;
        tma2d_stream(dst, m, 0, row, bar, pol);
        tma2d_stream(dst + BOX, m, 64, row, bar, pol);
        tma2d_stream(dst + 2 * BOX, m, 128, row, bar, pol);
        tma2d(dst + 3 * BOX, isk ? &me : &mf, row & (SEQ - 1), 0, bar);
    };

    if (threadIdx.x < 32 && elect_one()) {
        sts32(t0_s, now_ns());
        map_prefetch(&mk);
        map_prefetch(&me);
        mbar_init(full, 1);
        mbar_init(full + 8, 1);
        proxy_fence();
        const uint64_t pol = stream_policy();
        issue(0, pol);
        issue(1, pol);
    }
    const int warp = __shfl_sync(0xffffffffu, threadIdx.x >> 5, 0), lane = threadIdx.x & 31;
    if (warp == 9) {
        if (elect_one()) {
#pragma unroll
            for (int i = 0; i < CS; i++) mbar_init(cfull + 8 * i, i == CS - 1 ? 33 : 1);
            mbar_init(pready, 32);
            mbar_init(sready, 128);
            mbar_init(setup, 2);
            proxy_fence();
        }
    } else if (warp > 0 && elect_one()) {
#pragma unroll
        for (int i = 0; i < 4; i++) {
            if ((warp - 1) * 4 + i >= 2) mbar_init(full + 8 * ((warp - 1) * 4 + i), 1);
            mbar_init(empty + 8 * ((warp - 1) * 4 + i), 4);
        }
        proxy_fence();
    }
    __syncthreads();

    const int g = lane >> 2, t = lane & 3;
    if (warp == 8) {
        if (elect_one()) {
            mbar_expect_tx(setup, Q_BYTES);
            asm volatile("cp.async.bulk.shared::cluster.global.mbarrier::complete_tx::bytes [%0], [%1], %2, [%3];"
                         ::"r"(q_s), "l"(q), "r"(Q_BYTES), "r"(setup) : "memory");
            map_prefetch(&mv);
            map_prefetch(&mf);
            const uint64_t pol = stream_policy();
            const unsigned phase = cta * pace.tile >> 7;
            unsigned due = lds32(t0_s) - pace.lead + phase + 2 * pace.tile;
            int landed = 2;
#pragma unroll 1
            for (int i = 2; i < RT; i++) {
                unsigned now;
                for (int spins = 0;; spins++) {
                    now = now_ns();
                    if (landed < i && mbar_test(full + 8 * landed)) {
                        due += max((int)(now - lds32(iss_s + 4 * landed)) - pace.slack, 0) >> 3;
                        if (++landed == i) break;
                    }
                    if ((int)(now - due) >= 0) break;
                    if (spins > SPIN_LIMIT) __trap();
                }
                if (i >= NS) mbar_wait(empty + 8 * (i - NS));
                issue(i, pol);
                sts32(iss_s + 4 * i, now);
                due += pace.tile;
                if (i == KT - 4) l2_prefetch(f + cta * (R * SEQ / 128), R * SEQ / 64);
            }
            if (j < 3) {
                due += (cta * pace.box >> 7) - phase;
#pragma unroll 1
                for (int b = 0; b < CS; b++) {
                    const uint32_t early = b < 5 ? full + 8 * (RT - 1) : cfull + 8 * (b - 5);
                    for (int spins = 0; (int)(now_ns() - due) < 0 && !mbar_test(early); spins++)
                        if (spins > SPIN_LIMIT) __trap();
                    mbar_wait(empty + 8 * (RT + (b >> 2) - NS));
                    mbar_expect_tx(cfull + 8 * b, BOX);
                    tma2d_stream(s0 + b * BOX, &mv, j * 64, h * SEQ + TAIL_ROW + b * 64, cfull + 8 * b, pol);
                    due += pace.box;
                }
            }
        }
    } else if (warp == 9) {
        const unsigned epoch = __shfl_sync(0xffffffffu, lane == 0 ? sc->epoch[cta] + 1 : 0u, 0), par = epoch & 1;
        if (lane == 0) {
            sc->epoch[cta] = epoch;
            sts32(par_s, par);
            mbar_arrive(setup);
        }
        mbar_wait(sready);
        float2 s2 = make_float2(0.f, 0.f);
#pragma unroll
        for (int c = 0; c < 4; c++) {
            const float2 v = lds64f(s_s + 4 * R * c + 8 * lane);
            s2.x += v.x; s2.y += v.y;
        }
        const float scale = 0.07216878364870322f;
        s2.x *= scale; s2.y *= scale;
        float m = fmaxf(s2.x, s2.y);
#pragma unroll
        for (int o = 16; o; o >>= 1) m = fmaxf(m, __shfl_xor_sync(0xffffffffu, m, o));
        const float e0 = expf(s2.x - m), e1 = expf(s2.y - m);
        float sum = e0 + e1;
#pragma unroll
        for (int o = 16; o; o >>= 1) sum += __shfl_xor_sync(0xffffffffu, sum, o);
        const float inv = 1.0f / sum;
        sts64f(p_s + 8 * lane, e0 * inv, e1 * inv);
        mbar_arrive(pready);
        if (j < 3) {
            mbar_wait(cfull + 8 * (CS / 2));
            const float2 r = gather<4>(&sc->opart[h * 4 * D + 64 * j + 2 * lane], D, par);
            sts64f(r_s + 8 * lane, r.x, r.y);
            mbar_arrive(cfull + 8 * (CS - 1));
        }
    } else if (warp >= 4) {
        float acc[3][32];
#pragma unroll 1
        for (int i = KT; i < RT; i++) {
            mbar_wait(full + 8 * i);
            const uint32_t st = s0 + slot(i) * STAGE;
            const uint64_t da = make_desc(st, 16, 1024), db = make_desc(st + 3 * BOX, 16, 1024);
            wg_fence();
#pragma unroll
            for (int kk = 0; kk < 4; kk++) {
#pragma unroll
                for (int c = 0; c < 3; c++) wgmma_n64_at(acc[c], da + c * (BOX >> 4) + kk * 128, db + kk * 2, i > KT || kk > 0);
            }
            wg_commit();
            wg_wait0();
            if (lane == 0) mbar_arrive(empty + 8 * i);
        }
        mbar_wait(pready);
        const unsigned par = lds32(par_s);
        float2 p[8];
#pragma unroll
        for (int i = 0; i < 8; i++) p[i] = lds64f(p_s + 32 * i + 8 * t);
#pragma unroll
        for (int c = 0; c < 3; c++) {
            acc_fence<32>(acc[c]);
            float a0 = 0.f, a1 = 0.f, b0 = 0.f, b1 = 0.f;
#pragma unroll
            for (int i = 0; i < 8; i++) {
                a0 = fmaf(acc[c][4 * i], p[i].x, a0); a1 = fmaf(acc[c][4 * i + 1], p[i].y, a1);
                b0 = fmaf(acc[c][4 * i + 2], p[i].x, b0); b1 = fmaf(acc[c][4 * i + 3], p[i].y, b1);
            }
            const float a = quad_sum(a0 + a1), b = quad_sum(b0 + b1);
            if (t < 2) publish(&sc->opart[cta * D + 64 * c + (warp - 4) * 16 + g + 8 * t], t ? b : a, par);
        }
    } else {
        {
            float acc[96];
#pragma unroll 1
            for (int i = 0; i < KT; i++) {
                mbar_wait(full + 8 * i);
                const uint32_t st = s0 + slot(i) * STAGE;
                const uint64_t da = make_desc(st + 3 * BOX, 16, 1024), db = make_desc(st, BOX, 1024);
                wg_fence();
#pragma unroll
                for (int kk = 0; kk < 4; kk++) wgmma_n192_bt(acc, da + kk * 2, db + kk * 128, kk > 0);
                wg_commit();
                wg_wait0();
                if (lane == 0) mbar_arrive(empty + 8 * i);
                acc_fence<96>(acc);
                mbar_wait(setup);
                const int kt = ktile(i);
                uint32_t qr[24];
#pragma unroll
                for (int c = 0; c < 24; c++) qr[c] = lds32(q_s + (kt >> 6) * (D * 2) + 16 * c + 4 * t);
                float a0 = 0.f, a1 = 0.f, b0 = 0.f, b1 = 0.f;
#pragma unroll
                for (int c = 0; c < 24; c++) {
                    a0 = fmaf(acc[4 * c], bf_lo(qr[c]), a0); a1 = fmaf(acc[4 * c + 1], bf_hi(qr[c]), a1);
                    b0 = fmaf(acc[4 * c + 2], bf_lo(qr[c]), b0); b1 = fmaf(acc[4 * c + 3], bf_hi(qr[c]), b1);
                }
                const float a = quad_sum(a0 + a1), b = quad_sum(b0 + b1);
                if (t < 2) publish(&sc->score[kt * R + warp * 16 + g + 8 * t], t ? b : a, lds32(par_s));
            }
        }
        uint32_t fr[R];
        const uint32_t* fp = reinterpret_cast<const uint32_t*>(f + TAIL_ROW + warp * 64) + lane;
        auto load_f = [&] {
#pragma unroll
            for (int r = 0; r < R; r++) fr[r] = __ldg(fp + r * (SEQ / 2));
            fp += 128;
        };
        if (j < 3) load_f();
        mbar_wait(full + 8 * (SWEEP ? h / 2 + 4 : KT + 3));
        const float2 s2 = gather<16>(&sc->score[(h * 64 + warp * 16) * R + 2 * lane], R, lds32(par_s));
        sts64f(s_s + 4 * R * warp + 8 * lane, s2.x, s2.y);
        mbar_arrive(sready);
        if (j < 3) {
            mbar_wait(pready);
#pragma unroll 1
            for (int b = warp; b < CS; b += 4) {
                float w0 = 0.f, w1 = 0.f, w2 = 0.f, w3 = 0.f;
#pragma unroll
                for (int r = 0; r < R; r += 2) {
                    const float2 pv = lds64f(p_s + 4 * r);
                    w0 = fmaf(pv.x, bf_lo(fr[r]), w0); w1 = fmaf(pv.x, bf_hi(fr[r]), w1);
                    w2 = fmaf(pv.y, bf_lo(fr[r + 1]), w2); w3 = fmaf(pv.y, bf_hi(fr[r + 1]), w3);
                }
                w0 += w2; w1 += w3;
                if (b + 4 < CS) load_f();
                const __nv_bfloat162 hi = __floats2bfloat162_rn(w0, w1);
                const __nv_bfloat162 lo = __floats2bfloat162_rn(w0 - __low2float(hi), w1 - __high2float(hi));
                const uint32_t wd = w_s + 4 * (b * 64 + (g >> 2) * 32 + t * 8 + (g & 3));
                sts32(wd, *reinterpret_cast<const uint32_t*>(&hi));
                sts32(wd + 16, *reinterpret_cast<const uint32_t*>(&lo));
            }
            __syncwarp();
            asm volatile("barrier.sync 1, 128;" ::: "memory");

            float acc[4][4];
#pragma unroll
            for (int i = 0; i < 16; i++) acc[i >> 2][i & 3] = 0.f;
            uint32_t box = s0 + ((lane >> 4) * 8 + (lane & 7)) * 128 + (((2 * warp + ((lane >> 3) & 1)) ^ (lane & 7)) << 4);
            uint32_t wa = w_s + 16 * (2 * t + (g & 1)), bar = cfull;
            const int col = warp * 16 + g + 8 * (t & 1);
            uint64_t dst = (uint64_t)__cvta_generic_to_global(out + h * D + 64 * j + col);
            asm volatile("" : "+l"(dst));
#pragma unroll 1
            for (int b = 0; b < CS; b += 4) {
                float rest;
                uint4 w[8];
#pragma unroll
                for (int i = 0; i < 8; i++) w[i] = lds128(wa + 128 * i);
                uint32_t a[2][4][4];
#pragma unroll
                for (int u = 0; u <= 4; u++) {
                    if (u < 4) {
                        mbar_wait(bar + 8 * u);
#pragma unroll
                        for (int kk = 0; kk < 4; kk++) ldsm4t(a[u & 1][kk], box + u * BOX + kk * 2048);
                    }
                    if (u == 3) rest = __uint_as_float(lds32((b == CS - 4 ? r_s : p_s) + 4 * col));
                    if (u > 0) {
                        mma16816(acc[0], a[(u - 1) & 1][0], w[2 * u - 2].x, w[2 * u - 2].y);
                        mma16816(acc[1], a[(u - 1) & 1][1], w[2 * u - 2].z, w[2 * u - 2].w);
                        mma16816(acc[2], a[(u - 1) & 1][2], w[2 * u - 1].x, w[2 * u - 1].y);
                        mma16816(acc[3], a[(u - 1) & 1][3], w[2 * u - 1].z, w[2 * u - 1].w);
                    }
                }
                box += 4 * BOX; wa += 1024; bar += 32;
                float x[4];
#pragma unroll
                for (int i = 0; i < 4; i++) x[i] = (t & 1) ? acc[i][2] + acc[i][3] : acc[i][0] + acc[i][1];
                const float y = (((rest + x[0]) + x[1]) + x[2]) + x[3];
                asm volatile("{\n.reg .pred p;\nsetp.eq.s32 p, %2, %3;\n@p st.global.b16 [%0], %1;\n}"
                             ::"l"(dst), "h"(__bfloat16_as_ushort(__float2bfloat16(y))), "r"(b), "n"(CS - 4) : "memory");
            }
        }
    }
}

typedef CUresult (*EncodeFn)(CUtensorMap*, CUtensorMapDataType, cuuint32_t, void*, const cuuint64_t*, const cuuint64_t*,
                             const cuuint32_t*, const cuuint32_t*, CUtensorMapInterleave, CUtensorMapSwizzle,
                             CUtensorMapL2promotion, CUtensorMapFloatOOBfill);

static CUtensorMap make_map(EncodeFn enc, const void* p, uint64_t cols, uint64_t rows) {
    CUtensorMap m;
    cuuint64_t dims[2] = {cols, rows};
    cuuint64_t strides[1] = {cols * 2};
    cuuint32_t box[2] = {64, 64};
    cuuint32_t es[2] = {1, 1};
    enc(&m, CU_TENSOR_MAP_DATA_TYPE_BFLOAT16, 2, const_cast<void*>(p), dims, strides, box, es,
        CU_TENSOR_MAP_INTERLEAVE_NONE, CU_TENSOR_MAP_SWIZZLE_128B, CU_TENSOR_MAP_L2_PROMOTION_NONE,
        CU_TENSOR_MAP_FLOAT_OOB_FILL_NONE);
    return m;
}

static Pace make_pace() {
    int dev = 0, khz = 0, bits = 0;
    cudaGetDevice(&dev);
    cudaDeviceGetAttribute(&khz, cudaDevAttrMemoryClockRate, dev);
    cudaDeviceGetAttribute(&bits, cudaDevAttrGlobalMemoryBusWidth, dev);
    double tile = 964.0;
    if (khz > 0 && bits > 0) {
        const double bytes_per_ns = 2.0 * khz * 1e-6 * bits / 8.0;
        tile = 1.017 * (H * 4 * 3 * BOX + 4 * BOX) / bytes_per_ns;
    }
    return Pace{(int)tile, (int)(0.83 * tile), (int)(2.07 * tile), (int)(0.283 * tile)};
}

}

extern "C" void kernel_launch(void* const* d_in, const int* in_sizes, int n_in, void* d_out, int out_size) {
    using namespace lf;
    void* fn = nullptr;
    cudaDriverEntryPointQueryResult qr;
    cudaGetDriverEntryPoint("cuTensorMapEncodeTiled", &fn, cudaEnableDefault, &qr);
    EncodeFn enc = (EncodeFn)fn;
    const CUtensorMap mk = make_map(enc, d_in[1], D, (uint64_t)H * SEQ), mv = make_map(enc, d_in[2], D, (uint64_t)H * SEQ);
    const CUtensorMap me = make_map(enc, d_in[3], SEQ, R), mf = make_map(enc, d_in[4], SEQ, R);
    void* sc = nullptr;
    cudaGetSymbolAddress(&sc, g_scratch);
    int dev = 0, sms = 0;
    cudaGetDevice(&dev);
    cudaDeviceGetAttribute(&sms, cudaDevAttrMultiProcessorCount, dev);
    auto kern = sms >= H * 4 ? linformer_kernel<true> : linformer_kernel<false>;
    cudaFuncSetAttribute(kern, cudaFuncAttributeMaxDynamicSharedMemorySize, SMEM_BYTES);
    cudaLaunchAttribute coop = {};
    coop.id = cudaLaunchAttributeCooperative;
    coop.val.cooperative = sms >= H * 4;
    cudaLaunchConfig_t cfg = {};
    cfg.gridDim = dim3(H * 4);
    cfg.blockDim = dim3(320);
    cfg.dynamicSmemBytes = SMEM_BYTES;
    cfg.stream = cudaStreamPerThread;
    cfg.attrs = &coop;
    cfg.numAttrs = 1;
    cudaLaunchKernelEx(&cfg, kern, (const __nv_bfloat16*)d_in[1], (const __nv_bfloat16*)d_in[0], (const __nv_bfloat16*)d_in[4],
                       (__nv_bfloat16*)d_out, (Scratch*)sc, make_pace(), mk, me, mv, mf);
}
```
